```python
import torch

def _softmax(x, axis=-1):
    return torch.softmax(x, dim=axis)
def _gelu(x):
    return torch.nn.functional.gelu(x, approximate="tanh")
def _silu(x):
    return torch.nn.functional.silu(x)
def _sigmoid(x):
    return torch.sigmoid(x)
def _layernorm(x, axis=-1, eps=1e-5):
    m = x.mean(dim=axis, keepdim=True)
    v = x.var(dim=axis, keepdim=True, unbiased=False)
    return (x - m) / torch.sqrt(v + eps)
def _scatter_add(tgt, idx, src, axis=0):
    return tgt.clone().index_add_(axis, idx, src)
def _segment_sum(src, seg, n):
    out = torch.zeros((n,) + src.shape[1:], dtype=src.dtype)
    return out.index_add_(0, seg, src)
def _pad(x, pw):
    flat = tuple(v for pair in reversed(pw) for v in pair)
    return torch.nn.functional.pad(x, flat)

kernel_name = 'gated_mix__sliding_local_dilated__dense_activation_gelu__prompt'

def setup_inputs():

    _w = (lambda a: (lambda t: t.to(torch.bfloat16) if t.is_floating_point() else t)(torch.as_tensor(a)))
    def _A_setup():
        B, S, D = 1, 2048, 576
        return {
            "x": _w((lambda *s: torch.randn(*s, dtype=torch.bfloat16) * 0.05)(B, S, D)),
            "wqkv": _w((lambda *s: torch.randn(*s, dtype=torch.bfloat16) * 0.8)(D, 3 * D)),
            "wo": _w((lambda *s: torch.randn(*s, dtype=torch.bfloat16) * 0.05)(D, D)),
        }
    _A_in = _A_setup()

    def _B_setup():
        B, S, D, F = 1, 2048, 576, 4608
        return {
            "x": _w((lambda *s: torch.randn(*s, dtype=torch.bfloat16) * 0.05)(B, S, D)),
            "w1": _w((lambda *s: torch.randn(*s, dtype=torch.bfloat16) * 12.8)(D, F) * (D ** -0.5)),
            "b1": _w((lambda *s: torch.randn(*s, dtype=torch.bfloat16) * 12.8)(F) * 0.01),
            "w2": _w((lambda *s: torch.randn(*s, dtype=torch.bfloat16) * 1.6)(F, D) * (F ** -0.5)),
            "b2": _w((lambda *s: torch.randn(*s, dtype=torch.bfloat16) * 12.8)(D) * 0.01),
        }
    _B_in = _B_setup()

    return {
        "A_x": _A_in["x"],
        "A_wqkv": _A_in["wqkv"],
        "A_wo": _A_in["wo"],
        "B_x": _B_in["x"],
        "B_w1": _B_in["w1"],
        "B_b1": _B_in["b1"],
        "B_w2": _B_in["w2"],
        "B_b2": _B_in["b2"],
        "gate_w": _w((lambda *s: torch.randn(*s, dtype=torch.bfloat16) * 0.05)(576) * 16.0),
    }

def reference(A_x, A_wqkv, A_wo, B_x, B_w1, B_b1, B_w2, B_b2, gate_w):
    def _A_ref(x, wqkv, wo):
        B, S, D = x.shape
        H = 32; Dh = D // H
        W, dil = 8, 2
        qkv = (lambda x, *d: x.permute(*d))((x @ wqkv).reshape(B, S, 3, H, Dh), 2, 0, 3, 1, 4)
        q, k, v = qkv[0], qkv[1], qkv[2]
        scale = Dh ** -0.5
        pos = torch.arange(S)
        off = torch.arange(W) * dil
        idx = pos[:, None] - off[None, :]
        mask = idx >= 0
        idx_c = torch.where(mask, idx, 0).reshape(-1)
        kg = k[:, :, idx_c, :].reshape(B, H, S, W, Dh)
        vg = v[:, :, idx_c, :].reshape(B, H, S, W, Dh)
        logits = torch.einsum("bhsd,bhswd->bhsw", q, kg) * scale
        logits = torch.where(mask[None, None, :, :], logits, -1e9)
        attn = _softmax(logits, axis=-1)
        o = torch.einsum("bhsw,bhswd->bhsd", attn, vg)
        return (lambda x, *d: x.permute(*d))(o, 0, 2, 1, 3).reshape(B, S, D) @ wo

    def _B_ref(x, w1, b1, w2, b2):
        h = torch.einsum("bsd,df->bsf", x, w1) + b1
        h = _gelu(h)
        return torch.einsum("bsf,fd->bsd", h, w2) + b2

    x = A_x
    g = _sigmoid((x * gate_w).sum(-1, keepdims=True))
    a = _A_ref(x, A_wqkv, A_wo)
    b = _B_ref(x, B_w1, B_b1, B_w2, B_b2)
    return g * a + (1 - g) * b
```

```cpp
#include <cuda_runtime.h>
#include <cuda_bf16.h>
#include <cuda.h>
#include <stdint.h>
#include <type_traits>

namespace {

constexpr int D_ = 576;
constexpr int SLOT = 12288;
constexpr int OFF_X = 4096;
constexpr int OFF_RING = OFF_X + 147456;
constexpr int OFF_BAR = OFF_RING + 6 * SLOT;
constexpr int OFF_WO = 0;
constexpr int OFF_OT = OFF_WO + 9 * SLOT;
constexpr int B_FULL = OFF_BAR;
constexpr int B_EMPTY = B_FULL + 48;
constexpr int B_XFULL = B_EMPTY + 48;
constexpr int B_XDEAD = B_XFULL + 72;
constexpr int B_WO0 = B_XDEAD + 8;
constexpr int B_WO1 = B_WO0 + 8;
constexpr int B_GATE = B_WO1 + 8;
constexpr int B_QDONE = B_GATE + 8;
constexpr int B_XQDONE = B_QDONE + 8;
constexpr int B_PDONE = B_XQDONE + 8;
constexpr int B_PFULL = B_PDONE + 64;
constexpr int B_QKV = B_PFULL + 64;
constexpr int B_ODONE = B_QKV + 8;
constexpr int OFF_EPOCH = OFF_BAR + 384;
constexpr int OFF_G = OFF_BAR + 512;
constexpr int OFF_B1 = OFF_G + 512;
constexpr int OFF_B2 = OFF_B1 + 2304;
constexpr int OFF_GW = OFF_B2 + 512;
constexpr int SMEM_BYTES = OFF_GW + 1152;
constexpr int WIDE_ROUNDS = 6;
constexpr int QP = 1056;

__device__ __align__(128) uint32_t g_qs[864 * 2 * QP];
__device__ __align__(128) __nv_bfloat16 g_oT[D_ * 2048];
__device__ uint4 g_part[16 * 9 * 8 * 1024];
__device__ unsigned long long g_gate[2048];
__device__ uint32_t g_cnt[3 * 16 * 32];
__device__ uint32_t g_pflag[16 * 9 * 8 * 8];
__device__ unsigned long long g_ticket;

__device__ __forceinline__ uint32_t smem_u32(const void* p) { return (uint32_t)__cvta_generic_to_shared(p); }
__device__ __forceinline__ void mbar_init(uint32_t bar, uint32_t cnt) { asm volatile("mbarrier.init.shared::cta.b64 [%0], %1;" :: "r"(bar), "r"(cnt)); }
__device__ __forceinline__ void mbar_expect_tx(uint32_t bar, uint32_t bytes) { asm volatile("mbarrier.arrive.expect_tx.shared::cta.b64 _, [%0], %1;" :: "r"(bar), "r"(bytes) : "memory"); }
__device__ __forceinline__ void mbar_arrive(uint32_t bar) { asm volatile("mbarrier.arrive.shared::cta.b64 _, [%0];" :: "r"(bar) : "memory"); }
__device__ __forceinline__ void mbar_arrive_remote(uint32_t cluster_addr) { asm volatile("mbarrier.arrive.shared::cluster.b64 _, [%0];" :: "r"(cluster_addr) : "memory"); }
__device__ __forceinline__ uint32_t mapa(uint32_t addr, uint32_t cta) { uint32_t r; asm volatile("mapa.shared::cluster.u32 %0, %1, %2;" : "=r"(r) : "r"(addr), "r"(cta)); return r; }
__device__ __forceinline__ void mbar_wait(uint32_t bar, uint32_t parity) {
    asm volatile("{\n.reg .pred p;\n"
        "W_%=:\nmbarrier.try_wait.parity.shared::cta.b64 p, [%0], %1;\n@p bra D_%=;\n"
        "add.u32 spin_n, spin_n, 1;\nsetp.lt.u32 p, spin_n, 0x800000;\n@p bra W_%=;\nD_%=:\n}" :: "r"(bar), "r"(parity) : "memory");
}
__device__ __forceinline__ void tma3d(uint32_t dst, const CUtensorMap* m, int c0, int c1, int c2, uint32_t bar) {
    asm volatile("cp.async.bulk.tensor.3d.shared::cluster.global.mbarrier::complete_tx::bytes [%0], [%1, {%3, %4, %5}], [%2];"
        :: "r"(dst), "l"(m), "r"(bar), "r"(c0), "r"(c1), "r"(c2) : "memory");
}
__device__ __forceinline__ void tma3d_mc(uint32_t dst, const CUtensorMap* m, int c0, int c1, int c2, uint32_t bar) {
    asm volatile("cp.async.bulk.tensor.3d.shared::cluster.global.mbarrier::complete_tx::bytes.multicast::cluster [%0], [%1, {%3, %4, %5}], [%2], %6;"
        :: "r"(dst), "l"(m), "r"(bar), "r"(c0), "r"(c1), "r"(c2), "h"((uint16_t)3) : "memory");
}
__device__ __forceinline__ void bulk_load(uint32_t dst, const void* src, uint32_t bytes, uint32_t bar) {
    asm volatile("cp.async.bulk.shared::cluster.global.mbarrier::complete_tx::bytes [%0], [%1], %2, [%3];"
        :: "r"(dst), "l"(src), "r"(bytes), "r"(bar) : "memory");
}
__device__ __forceinline__ void wgmma_fence() { asm volatile("wgmma.fence.sync.aligned;" ::: "memory"); }
__device__ __forceinline__ void wgmma_commit() { asm volatile("wgmma.commit_group.sync.aligned;" ::: "memory"); }
template <int N> __device__ __forceinline__ void wgmma_wait() { asm volatile("wgmma.wait_group.sync.aligned %0;" :: "n"(N) : "memory"); }
__device__ __forceinline__ uint32_t desc_lo(uint32_t addr, uint32_t lbo) { return ((addr & 0x3FFFF) >> 4) | ((lbo >> 4) << 16); }
template <int N> __device__ __forceinline__ void fence_regs(float (&a)[N]) {
#pragma unroll
    for (int i = 0; i < N; i++) asm volatile("" : "+f"(a[i]) :: "memory");
}
template <int I, int N, class F> __device__ __forceinline__ void static_for(F f) {
    if constexpr (I < N) { f(std::integral_constant<int, I>{}); static_for<I + 1, N>(f); }
}
__device__ __forceinline__ uint32_t pack_bf16(float lo, float hi) {
    uint32_t r; asm("cvt.rn.bf16x2.f32 %0, %1, %2;" : "=r"(r) : "f"(hi), "f"(lo)); return r;
}
__device__ __forceinline__ float bf_lo(uint32_t w) { return __uint_as_float(w << 16); }
__device__ __forceinline__ float bf_hi(uint32_t w) { return __uint_as_float(w & 0xffff0000u); }
__device__ __forceinline__ float ex2f(float x) { float r; asm("ex2.approx.ftz.f32 %0, %1;" : "=f"(r) : "f"(x)); return r; }
__device__ __forceinline__ uint32_t ld_acquire(const uint32_t* p) { uint32_t v; asm volatile("ld.acquire.gpu.global.u32 %0, [%1];" : "=r"(v) : "l"(p) : "memory"); return v; }
__device__ __forceinline__ void st_release(uint32_t* p, uint32_t v) { asm volatile("st.release.gpu.global.u32 [%0], %1;" :: "l"(p), "r"(v) : "memory"); }
__device__ __forceinline__ void red_release_add(uint32_t* p, uint32_t v) { asm volatile("red.release.gpu.global.add.u32 [%0], %1;" :: "l"(p), "r"(v) : "memory"); }
__device__ __forceinline__ void fence_proxy_async() { asm volatile("fence.proxy.async;" ::: "memory"); }
__device__ __forceinline__ void wait_flag(const uint32_t* p, uint32_t target) {
    _Pragma("unroll 1") for (int n = 0; n < (1 << 22); n++) {
        if ((int)(ld_acquire(p) - target) >= 0) break;
    }
}
__device__ __forceinline__ float2 lds_f2(uint32_t a) { float2 v; asm volatile("ld.shared.v2.f32 {%0, %1}, [%2];" : "=f"(v.x), "=f"(v.y) : "r"(a)); return v; }
__device__ __forceinline__ float lds_f(uint32_t a) { float v; asm volatile("ld.shared.f32 %0, [%1];" : "=f"(v) : "r"(a)); return v; }
__device__ __forceinline__ uint4 lds_u4(uint32_t a) { uint4 v; asm volatile("ld.shared.v4.u32 {%0, %1, %2, %3}, [%4];" : "=r"(v.x), "=r"(v.y), "=r"(v.z), "=r"(v.w) : "r"(a) : "memory"); return v; }
__device__ __forceinline__ void sts_f(uint32_t a, float v) { asm volatile("st.shared.f32 [%0], %1;" :: "r"(a), "f"(v) : "memory"); }

__constant__ uint32_t c_desc_hi[8] = {0x40000040u, 0, 0, 0, 0x40000040u, 0, 0, 0};
template <int OP> __device__ __forceinline__ uint64_t desc64(uint32_t lo) { return ((uint64_t)c_desc_hi[OP * 4] << 32) | lo; }
__host__ __device__ constexpr int xoff(int k) { return k < 0 ? 0 : (k >> 2) * 16384 + (k & 3) * 32; }
__host__ __device__ constexpr int roff6(int k) { return k < 0 ? 0 : k * 2048; }
__host__ __device__ constexpr int roff3(int k) { return k < 0 ? 0 : ((k / 3) % 6) * SLOT + (k % 3) * 2048; }
template <int DA, int DB> __device__ __forceinline__ void wgmma_ssi_n128(float (&d)[64], uint64_t& da, uint64_t& db, int scale_d) {
    asm volatile("{\n.reg .pred p;\n.reg .b32 l, h;\nsetp.ne.b32 p, %66, 0;\nmov.b64 {l, h}, %64;\nadd.s32 l, l, %67;\nmov.b64 %64, {l, h};\nmov.b64 {l, h}, %65;\nadd.s32 l, l, %68;\nmov.b64 %65, {l, h};\n"
        "wgmma.mma_async.sync.aligned.m64n128k16.f32.bf16.bf16 {%0, %1, %2, %3, %4, %5, %6, %7, %8, %9, %10, %11, %12, %13, %14, %15, %16, %17, %18, %19, %20, %21, %22, %23, %24, %25, %26, %27, %28, %29, %30, %31, %32, %33, %34, %35, %36, %37, %38, %39, %40, %41, %42, %43, %44, %45, %46, %47, %48, %49, %50, %51, %52, %53, %54, %55, %56, %57, %58, %59, %60, %61, %62, %63}, %64, %65, p, 1, 1, 0, 1;\n}"
        : "+f"(d[0]), "+f"(d[1]), "+f"(d[2]), "+f"(d[3]), "+f"(d[4]), "+f"(d[5]), "+f"(d[6]), "+f"(d[7]), "+f"(d[8]), "+f"(d[9]), "+f"(d[10]), "+f"(d[11]), "+f"(d[12]), "+f"(d[13]), "+f"(d[14]), "+f"(d[15]), "+f"(d[16]), "+f"(d[17]), "+f"(d[18]), "+f"(d[19]), "+f"(d[20]), "+f"(d[21]), "+f"(d[22]), "+f"(d[23]), "+f"(d[24]), "+f"(d[25]), "+f"(d[26]), "+f"(d[27]), "+f"(d[28]), "+f"(d[29]), "+f"(d[30]), "+f"(d[31]), "+f"(d[32]), "+f"(d[33]), "+f"(d[34]), "+f"(d[35]), "+f"(d[36]), "+f"(d[37]), "+f"(d[38]), "+f"(d[39]), "+f"(d[40]), "+f"(d[41]), "+f"(d[42]), "+f"(d[43]), "+f"(d[44]), "+f"(d[45]), "+f"(d[46]), "+f"(d[47]), "+f"(d[48]), "+f"(d[49]), "+f"(d[50]), "+f"(d[51]), "+f"(d[52]), "+f"(d[53]), "+f"(d[54]), "+f"(d[55]), "+f"(d[56]), "+f"(d[57]), "+f"(d[58]), "+f"(d[59]), "+f"(d[60]), "+f"(d[61]), "+f"(d[62]), "+f"(d[63]), "+l"(da), "+l"(db)
        : "r"(scale_d), "n"(DA / 16), "n"(DB / 16));
}
template <int DA, int DB> __device__ __forceinline__ void wgmma_ssi_n64(float (&d)[32], uint64_t& da, uint64_t& db, int scale_d) {
    asm volatile("{\n.reg .pred p;\n.reg .b32 l, h;\nsetp.ne.b32 p, %34, 0;\nmov.b64 {l, h}, %32;\nadd.s32 l, l, %35;\nmov.b64 %32, {l, h};\nmov.b64 {l, h}, %33;\nadd.s32 l, l, %36;\nmov.b64 %33, {l, h};\n"
        "wgmma.mma_async.sync.aligned.m64n64k16.f32.bf16.bf16 {%0, %1, %2, %3, %4, %5, %6, %7, %8, %9, %10, %11, %12, %13, %14, %15, %16, %17, %18, %19, %20, %21, %22, %23, %24, %25, %26, %27, %28, %29, %30, %31}, %32, %33, p, 1, 1, 0, 1;\n}"
        : "+f"(d[0]), "+f"(d[1]), "+f"(d[2]), "+f"(d[3]), "+f"(d[4]), "+f"(d[5]), "+f"(d[6]), "+f"(d[7]), "+f"(d[8]), "+f"(d[9]), "+f"(d[10]), "+f"(d[11]), "+f"(d[12]), "+f"(d[13]), "+f"(d[14]), "+f"(d[15]), "+f"(d[16]), "+f"(d[17]), "+f"(d[18]), "+f"(d[19]), "+f"(d[20]), "+f"(d[21]), "+f"(d[22]), "+f"(d[23]), "+f"(d[24]), "+f"(d[25]), "+f"(d[26]), "+f"(d[27]), "+f"(d[28]), "+f"(d[29]), "+f"(d[30]), "+f"(d[31]), "+l"(da), "+l"(db)
        : "r"(scale_d), "n"(DA / 16), "n"(DB / 16));
}
template <int DB> __device__ __forceinline__ void wgmma_rsi_n64(float (&d)[32], uint32_t a0, uint32_t a1, uint32_t a2, uint32_t a3, uint64_t& db, int scale_d) {
    asm volatile("{\n.reg .pred p;\n.reg .b32 l, h;\nsetp.ne.b32 p, %37, 0;\nmov.b64 {l, h}, %32;\nadd.s32 l, l, %38;\nmov.b64 %32, {l, h};\n"
        "wgmma.mma_async.sync.aligned.m64n64k16.f32.bf16.bf16 {%0, %1, %2, %3, %4, %5, %6, %7, %8, %9, %10, %11, %12, %13, %14, %15, %16, %17, %18, %19, %20, %21, %22, %23, %24, %25, %26, %27, %28, %29, %30, %31}, {%33, %34, %35, %36}, %32, p, 1, 1, 1;\n}"
        : "+f"(d[0]), "+f"(d[1]), "+f"(d[2]), "+f"(d[3]), "+f"(d[4]), "+f"(d[5]), "+f"(d[6]), "+f"(d[7]), "+f"(d[8]), "+f"(d[9]), "+f"(d[10]), "+f"(d[11]), "+f"(d[12]), "+f"(d[13]), "+f"(d[14]), "+f"(d[15]), "+f"(d[16]), "+f"(d[17]), "+f"(d[18]), "+f"(d[19]), "+f"(d[20]), "+f"(d[21]), "+f"(d[22]), "+f"(d[23]), "+f"(d[24]), "+f"(d[25]), "+f"(d[26]), "+f"(d[27]), "+f"(d[28]), "+f"(d[29]), "+f"(d[30]), "+f"(d[31]), "+l"(db)
        : "r"(a0), "r"(a1), "r"(a2), "r"(a3), "r"(scale_d), "n"(DB / 16));
}
template <int OA, int OB> __device__ __forceinline__ void wgmma_ss_n192(float (&d)[96], uint32_t la, uint32_t lb, int scale_d) {
    asm volatile("{\n.reg .pred p;\n.reg .b32 ta, tb;\n.reg .b64 da, db;\nsetp.ne.b32 p, %98, 0;\n"
        "add.u32 ta, %96, %99;\nmov.b64 da, {ta, 0x40000040};\nadd.u32 tb, %97, %100;\nmov.b64 db, {tb, 0x40000040};\n"
        "wgmma.mma_async.sync.aligned.m64n192k16.f32.bf16.bf16 {%0, %1, %2, %3, %4, %5, %6, %7, %8, %9, %10, %11, %12, %13, %14, %15, %16, %17, %18, %19, %20, %21, %22, %23, %24, %25, %26, %27, %28, %29, %30, %31, %32, %33, %34, %35, %36, %37, %38, %39, %40, %41, %42, %43, %44, %45, %46, %47, %48, %49, %50, %51, %52, %53, %54, %55, %56, %57, %58, %59, %60, %61, %62, %63, %64, %65, %66, %67, %68, %69, %70, %71, %72, %73, %74, %75, %76, %77, %78, %79, %80, %81, %82, %83, %84, %85, %86, %87, %88, %89, %90, %91, %92, %93, %94, %95}, da, db, p, 1, 1, 0, 1;\n}"
        : "+f"(d[0]), "+f"(d[1]), "+f"(d[2]), "+f"(d[3]), "+f"(d[4]), "+f"(d[5]), "+f"(d[6]), "+f"(d[7]), "+f"(d[8]), "+f"(d[9]), "+f"(d[10]), "+f"(d[11]), "+f"(d[12]), "+f"(d[13]), "+f"(d[14]), "+f"(d[15]), "+f"(d[16]), "+f"(d[17]), "+f"(d[18]), "+f"(d[19]), "+f"(d[20]), "+f"(d[21]), "+f"(d[22]), "+f"(d[23]), "+f"(d[24]), "+f"(d[25]), "+f"(d[26]), "+f"(d[27]), "+f"(d[28]), "+f"(d[29]), "+f"(d[30]), "+f"(d[31]), "+f"(d[32]), "+f"(d[33]), "+f"(d[34]), "+f"(d[35]), "+f"(d[36]), "+f"(d[37]), "+f"(d[38]), "+f"(d[39]), "+f"(d[40]), "+f"(d[41]), "+f"(d[42]), "+f"(d[43]), "+f"(d[44]), "+f"(d[45]), "+f"(d[46]), "+f"(d[47]), "+f"(d[48]), "+f"(d[49]), "+f"(d[50]), "+f"(d[51]), "+f"(d[52]), "+f"(d[53]), "+f"(d[54]), "+f"(d[55]), "+f"(d[56]), "+f"(d[57]), "+f"(d[58]), "+f"(d[59]), "+f"(d[60]), "+f"(d[61]), "+f"(d[62]), "+f"(d[63]), "+f"(d[64]), "+f"(d[65]), "+f"(d[66]), "+f"(d[67]), "+f"(d[68]), "+f"(d[69]), "+f"(d[70]), "+f"(d[71]), "+f"(d[72]), "+f"(d[73]), "+f"(d[74]), "+f"(d[75]), "+f"(d[76]), "+f"(d[77]), "+f"(d[78]), "+f"(d[79]), "+f"(d[80]), "+f"(d[81]), "+f"(d[82]), "+f"(d[83]), "+f"(d[84]), "+f"(d[85]), "+f"(d[86]), "+f"(d[87]), "+f"(d[88]), "+f"(d[89]), "+f"(d[90]), "+f"(d[91]), "+f"(d[92]), "+f"(d[93]), "+f"(d[94]), "+f"(d[95])
        : "r"(la), "r"(lb), "r"(scale_d), "n"(OA / 16), "n"(OB / 16));
}
template <int OA, int OB> __device__ __forceinline__ void wgmma_ss_n64(float (&d)[32], uint32_t la, uint32_t lb, int scale_d) {
    asm volatile("{\n.reg .pred p;\n.reg .b32 ta, tb;\n.reg .b64 da, db;\nsetp.ne.b32 p, %34, 0;\n"
        "add.u32 ta, %32, %35;\nmov.b64 da, {ta, 0x40000040};\nadd.u32 tb, %33, %36;\nmov.b64 db, {tb, 0x40000040};\n"
        "wgmma.mma_async.sync.aligned.m64n64k16.f32.bf16.bf16 {%0, %1, %2, %3, %4, %5, %6, %7, %8, %9, %10, %11, %12, %13, %14, %15, %16, %17, %18, %19, %20, %21, %22, %23, %24, %25, %26, %27, %28, %29, %30, %31}, da, db, p, 1, 1, 0, 1;\n}"
        : "+f"(d[0]), "+f"(d[1]), "+f"(d[2]), "+f"(d[3]), "+f"(d[4]), "+f"(d[5]), "+f"(d[6]), "+f"(d[7]), "+f"(d[8]), "+f"(d[9]), "+f"(d[10]), "+f"(d[11]), "+f"(d[12]), "+f"(d[13]), "+f"(d[14]), "+f"(d[15]), "+f"(d[16]), "+f"(d[17]), "+f"(d[18]), "+f"(d[19]), "+f"(d[20]), "+f"(d[21]), "+f"(d[22]), "+f"(d[23]), "+f"(d[24]), "+f"(d[25]), "+f"(d[26]), "+f"(d[27]), "+f"(d[28]), "+f"(d[29]), "+f"(d[30]), "+f"(d[31])
        : "r"(la), "r"(lb), "r"(scale_d), "n"(OA / 16), "n"(OB / 16));
}
template <int OA, int OB> __device__ __forceinline__ void wgmma_ssT_n64(float (&d)[32], uint32_t la, uint32_t lb, int scale_d) {
    asm volatile("{\n.reg .pred p;\n.reg .b32 ta, tb;\n.reg .b64 da, db;\nsetp.ne.b32 p, %34, 0;\n"
        "add.u32 ta, %32, %35;\nmov.b64 da, {ta, 0x40000040};\nadd.u32 tb, %33, %36;\nmov.b64 db, {tb, 0x40000040};\n"
        "wgmma.mma_async.sync.aligned.m64n64k16.f32.bf16.bf16 {%0, %1, %2, %3, %4, %5, %6, %7, %8, %9, %10, %11, %12, %13, %14, %15, %16, %17, %18, %19, %20, %21, %22, %23, %24, %25, %26, %27, %28, %29, %30, %31}, da, db, p, 1, 1, 1, 1;\n}"
        : "+f"(d[0]), "+f"(d[1]), "+f"(d[2]), "+f"(d[3]), "+f"(d[4]), "+f"(d[5]), "+f"(d[6]), "+f"(d[7]), "+f"(d[8]), "+f"(d[9]), "+f"(d[10]), "+f"(d[11]), "+f"(d[12]), "+f"(d[13]), "+f"(d[14]), "+f"(d[15]), "+f"(d[16]), "+f"(d[17]), "+f"(d[18]), "+f"(d[19]), "+f"(d[20]), "+f"(d[21]), "+f"(d[22]), "+f"(d[23]), "+f"(d[24]), "+f"(d[25]), "+f"(d[26]), "+f"(d[27]), "+f"(d[28]), "+f"(d[29]), "+f"(d[30]), "+f"(d[31])
        : "r"(la), "r"(lb), "r"(scale_d), "n"(OA / 16), "n"(OB / 16));
}


__device__ __forceinline__ float gelu_scaled(float v, float hs) {
    const float c1 = 0.7978845608028654f, c2 = 0.7978845608028654f * 0.044715f;
    float t;
    asm("tanh.approx.f32 %0, %1;" : "=f"(t) : "f"(v * fmaf(v * v, c2, c1)));
    const float hv = v * hs;
    return fmaf(hv, t, hv);
}

struct Params {
    const __nv_bfloat16* b1;
    const __nv_bfloat16* b2;
    const __nv_bfloat16* gate_w;
    const __nv_bfloat16* w1;
    const __nv_bfloat16* w2;
    const __nv_bfloat16* wo;
    __nv_bfloat16* out;
};


template <int Q0, int Q1, class Pre, class Epi>
__device__ __forceinline__ void tile_ss(float (&acc)[32], uint32_t sb, uint32_t da0, uint32_t db0, uint32_t ph, uint32_t rel, bool do_rel, Pre pre, Epi epi) {
    uint64_t da = desc64<0>(da0), db = desc64<1>(db0);
    static_for<Q0, Q1>([&](auto qc) {
        constexpr int q = qc.value;
        pre(q);
        wgmma_fence();
        static_for<0, 6>([&](auto kc) {
            constexpr int k = q * 6 + kc.value;
            wgmma_ssi_n64<xoff(k) - xoff(k - 1), roff6(k) - roff6(k - 1)>(acc, da, db, k > 0);
        });
        wgmma_commit();
        mbar_wait(sb + B_FULL + ((q + 1) % 6) * 8, q == 5 ? ph ^ 1 : ph);
        wgmma_wait<1>();
        if (do_rel) mbar_arrive_remote(rel + ((q + 5) % 6) * 8);
        epi(q);
    });
}

template <int I0, int I1, class Epi>
__device__ __forceinline__ void tile128(float (&acc)[64], uint32_t sb, uint32_t da0, uint32_t db1, uint32_t ph, uint32_t rel, bool do_rel, Epi epi) {
    uint64_t da = desc64<0>(da0), db = desc64<1>(db1);
    static_for<I0, I1>([&](auto ic) {
        constexpr int i = ic.value, q = i % 6;
        wgmma_fence();
        static_for<0, 3>([&](auto kc) {
            constexpr int k = i * 3 + kc.value;
            wgmma_ssi_n128<xoff(k) - xoff(k - 1), roff3(k) - roff3(k - 1)>(acc, da, db, k > 0);
        });
        wgmma_commit();
        mbar_wait(sb + B_FULL + ((q + 1) % 6) * 8, (i >= 5 && i < 11) ? ph ^ 1 : ph);
        wgmma_wait<1>();
        if (do_rel) mbar_arrive_remote(rel + ((q + 5) % 6) * 8);
        if (i < 11) epi(i + 1);
    });
}

template <class Epi>
__device__ __forceinline__ void pass_rs(float (&acc)[32], const uint32_t (&h)[128], uint32_t sb, uint32_t da0, uint32_t db0, uint32_t dot, uint32_t dwo,
                                        bool typeB, uint32_t wobar, uint32_t ph, uint32_t rel, bool do_rel, bool more, Epi epi) {
    uint64_t db = desc64<1>(db0);
    static_for<0, 6>([&](auto qc) {
        constexpr int q = qc.value;
        wgmma_fence();
        static_for<0, 6>([&](auto kc) {
            constexpr int k = q * 6 + kc.value;
            if constexpr (k < 32) wgmma_rsi_n64<roff6(k) - roff6(k - 1)>(acc, h[k * 4], h[k * 4 + 1], h[k * 4 + 2], h[k * 4 + 3], db, k > 0);
            else wgmma_ss_n64<8 * 16384 + (k & 3) * 32, q * SLOT + kc.value * 2048>(acc, da0, db0, 1);
        });
        wgmma_commit();
        if constexpr (q < 5) mbar_wait(sb + B_FULL + (q + 1) * 8, ph);
        else mbar_wait(wobar, 0);
        if constexpr (q > 0) {
            wgmma_wait<1>();
            if (do_rel && more) mbar_arrive_remote(rel + (q - 1) * 8);
        }
        epi(q);
    });
    wgmma_fence();
    static_for<0, 2>([&](auto sc) { wgmma_ssT_n64<sc.value * 2048, sc.value * 2048>(acc, dot, dwo, 1); });
    wgmma_commit();
    if (!typeB) {
        wgmma_fence();
        static_for<2, 6>([&](auto sc) { wgmma_ssT_n64<sc.value * 2048, sc.value * 2048>(acc, dot, dwo, 1); });
        wgmma_commit();
    }
    if (more) mbar_wait(sb + B_FULL, ph ^ 1);
    wgmma_wait<1>();
    if (do_rel && more) mbar_arrive_remote(rel + 5 * 8);
    wgmma_wait<0>();
}

__global__ void __cluster_dims__(2, 1, 1) __launch_bounds__(384, 1)
fused_kernel(const __grid_constant__ CUtensorMap mx, const __grid_constant__ CUtensorMap mq3, const __grid_constant__ CUtensorMap mq1,
             const __grid_constant__ CUtensorMap mw1, const __grid_constant__ CUtensorMap mw2,
             const __grid_constant__ CUtensorMap mwoA, const __grid_constant__ CUtensorMap mwoB,
             const __grid_constant__ CUtensorMap moA, const __grid_constant__ CUtensorMap moB, const Params prm) {
    extern __shared__ __align__(1024) uint8_t smem_raw[];
    asm volatile(".reg .b32 spin_n;\nmov.u32 spin_n, 0;" ::: "memory");
    const uint32_t sb = smem_u32(smem_raw);
    const int tid = threadIdx.x, warp = __shfl_sync(0xffffffff, tid >> 5, 0), lane = tid & 31;
    const int rank = blockIdx.x & 1, cl = blockIdx.x >> 1;
    const int m = (cl & 7) * 2 + rank, j = cl >> 3;
    const bool typeB = j >= 5;

    if (tid == 256) {
        for (int i = 0; i < 6; i++) mbar_init(sb + B_FULL + i * 8, 1);
        for (int i = 0; i < 9; i++) mbar_init(sb + B_XFULL + i * 8, 1);
        asm volatile("fence.mbarrier_init.release.cluster;" ::: "memory");
        asm volatile("fence.proxy.async.shared::cta;" ::: "memory");
    } else if (tid == 288) {
        for (int i = 0; i < 6; i++) mbar_init(sb + B_EMPTY + i * 8, 4);
        mbar_init(sb + B_XDEAD, 4); mbar_init(sb + B_WO0, 1); mbar_init(sb + B_WO1, 1); mbar_init(sb + B_GATE, 1);
        mbar_init(sb + B_QDONE, 8); mbar_init(sb + B_XQDONE, 1); mbar_init(sb + B_QKV, 1); mbar_init(sb + B_ODONE, 8);
        asm volatile("fence.mbarrier_init.release.cluster;" ::: "memory");
    } else if (tid == 352) {
        for (int i = 0; i < 8; i++) { mbar_init(sb + B_PDONE + i * 8, 8); mbar_init(sb + B_PFULL + i * 8, 1); }
        asm volatile("fence.mbarrier_init.release.cluster;" ::: "memory");
    } else if (tid == 320) {
        asm volatile("prefetch.tensormap [%0];" :: "l"(&mx) : "memory");
        asm volatile("prefetch.tensormap [%0];" :: "l"(&mq3) : "memory");
        asm volatile("prefetch.tensormap [%0];" :: "l"(&mw1) : "memory");
        asm volatile("prefetch.tensormap [%0];" :: "l"(&mq1) : "memory");
    }
    __syncthreads();
    asm volatile("barrier.cluster.arrive.relaxed.aligned;" ::: "memory");
    if (tid == 256) {
#pragma unroll 1
        for (int kb = 0; kb < 3; kb++) {
            mbar_expect_tx(sb + B_XFULL + kb * 8, 16384);
            tma3d(sb + OFF_X + kb * 16384, &mx, kb * 64, m * 64, 0, sb + B_XFULL + kb * 8);
#pragma unroll 1
            for (int s = 2 * kb; s < 2 * kb + 2; s++) {
                mbar_expect_tx(sb + B_FULL + s * 8, SLOT);
                tma3d(sb + OFF_RING + s * SLOT, &mq3, 0, s * 32, 3 * j, sb + B_FULL + s * 8);
                tma3d(sb + OFF_RING + s * SLOT + 6144, &mq3, 0, s * 32 + 16, 3 * j, sb + B_FULL + s * 8);
            }
        }
    }
    __syncwarp();
    asm volatile("barrier.cluster.wait.aligned;" ::: "memory");

    if (warp >= 8) {
        asm volatile("setmaxnreg.dec.sync.aligned.u32 40;");
        if (warp == 8) {
            if (lane == 0) {
                uint32_t ph = 0;
                const uint32_t dst = sb + OFF_RING + rank * 6144;
                _Pragma("unroll 1") for (int i = 6; i < 18; i++) {
                    const int s = i % 6;
                    if (!(i & 1)) {
                        const int kb = i >> 1;
                        mbar_expect_tx(sb + B_XFULL + kb * 8, 16384);
                        tma3d(sb + OFF_X + kb * 16384, &mx, kb * 64, m * 64, 0, sb + B_XFULL + kb * 8);
                    }
                    mbar_wait(sb + B_EMPTY + s * 8, ph);
                    mbar_expect_tx(sb + B_FULL + s * 8, SLOT);
                    tma3d_mc(dst + s * SLOT, &mq3, 0, i * 32 + rank * 16, 3 * j, sb + B_FULL + s * 8);
                    if (s == 5) ph ^= 1;
                }
#pragma unroll 1
                for (int t = typeB ? -1 : 0; t < 18; t++) {
                    const CUtensorMap* mp = t < 0 ? &mq1 : (t < 9 ? &mw1 : &mw2);
                    const bool wide = t >= 0 && t < WIDE_ROUNDS;
                    const int grp = t < 0 ? 19 + j : (wide ? 9 * j + (t & 6) + rank : (t < 9 ? 9 * j + t : (t == 9 ? 8 : ((j + t - 9) & 7))));
                    const int row0 = wide ? (t & 1) * 288 : (t < 9 ? 0 : 576 * j) + rank * 48;
                    const int step = wide ? 48 : 96;
#pragma unroll 1
                    for (int s = 0; s < 6; s++) {
                        mbar_wait(sb + B_EMPTY + s * 8, ph);
                        mbar_expect_tx(sb + B_FULL + s * 8, SLOT);
                        tma3d_mc(dst + s * SLOT, mp, 0, row0 + s * step, grp, sb + B_FULL + s * 8);
                    }
                    ph ^= 1;
                }
            }
        } else {
            const int hw = warp - 9;
            uint32_t* cntA = g_cnt, * cntO = g_cnt + 16 * 32;
            uint32_t epoch = 0;
            if (hw < 2) {
                mbar_wait(sb + B_XQDONE, 0);
                asm volatile("ld.shared.u32 %0, [%1];" : "=r"(epoch) : "r"(sb + OFF_EPOCH) : "memory");
                if (hw == 0) {
                    const int c = lane & 3, rr = lane >> 2;
                    float z0 = 0.f, z1 = 0.f;
                    auto dot8 = [](uint4 x, uint4 w, float t) {
                        t = fmaf(bf_lo(x.x), bf_lo(w.x), t); t = fmaf(bf_hi(x.x), bf_hi(w.x), t);
                        t = fmaf(bf_lo(x.y), bf_lo(w.y), t); t = fmaf(bf_hi(x.y), bf_hi(w.y), t);
                        t = fmaf(bf_lo(x.z), bf_lo(w.z), t); t = fmaf(bf_hi(x.z), bf_hi(w.z), t);
                        t = fmaf(bf_lo(x.w), bf_lo(w.w), t); return fmaf(bf_hi(x.w), bf_hi(w.w), t);
                    };
#pragma unroll 1
                    for (int kb = 0; kb < 9; kb++) {
                        const uint4 w0 = lds_u4(sb + OFF_GW + kb * 128 + c * 16), w1 = lds_u4(sb + OFF_GW + kb * 128 + 64 + c * 16);
                        mbar_wait(sb + B_XFULL + kb * 8, 0);
                        const uint32_t a = sb + OFF_X + kb * 16384 + j * 2048 + rr * 128;
                                                const uint4 x0 = lds_u4(a + ((c ^ rr) << 4)), x1 = lds_u4(a + (((c + 4) ^ rr) << 4));
                        const uint4 x2 = lds_u4(a + 1024 + ((c ^ rr) << 4)), x3 = lds_u4(a + 1024 + (((c + 4) ^ rr) << 4));
                        z0 = dot8(x1, w1, dot8(x0, w0, z0));
                        z1 = dot8(x3, w1, dot8(x2, w0, z1));
                    }
                    z0 += __shfl_xor_sync(0xffffffff, z0, 1); z1 += __shfl_xor_sync(0xffffffff, z1, 1);
                    z0 += __shfl_xor_sync(0xffffffff, z0, 2); z1 += __shfl_xor_sync(0xffffffff, z1, 2);
                    if (c < 2) {
                        const float g = __fdividef(1.0f, 1.0f + __expf(-(c ? z1 : z0)));
                        const unsigned long long v = ((unsigned long long)epoch << 32) | __float_as_uint(g);
                        asm volatile("st.relaxed.gpu.global.u64 [%0], %1;" :: "l"(g_gate + m * 128 + j * 16 + c * 8 + rr), "l"(v) : "memory");
                    }
#pragma unroll 1
                    for (int n = 0; n < (1 << 20); n++) {
                        unsigned long long v[4];
#pragma unroll
                        for (int i = 0; i < 4; i++) asm volatile("ld.relaxed.gpu.global.u64 %0, [%1];" : "=l"(v[i]) : "l"(g_gate + m * 128 + i * 32 + lane) : "memory");
                        bool ok = true;
#pragma unroll
                        for (int i = 0; i < 4; i++) {
                            ok = ok && (uint32_t)(v[i] >> 32) == epoch;
                            sts_f(sb + OFF_G + (i * 32 + lane) * 4, __uint_as_float((uint32_t)v[i]));
                        }
                        if (__all_sync(0xffffffff, ok)) break;
                    }
                    __syncwarp();
                    if (lane == 0) { mbar_arrive(sb + B_GATE); }
                }
            } else {
                if (lane == 0) epoch = (uint32_t)(atomicAdd(&g_ticket, 1ull) >> 7) + 1u;
                {
                    const uint32_t* b1w = reinterpret_cast<const uint32_t*>(prm.b1 + 576 * j);
                    const uint32_t* b2w = reinterpret_cast<const uint32_t*>(prm.b2);
                    uint32_t t1[9], tg[9];
#pragma unroll
                    for (int i = 0; i < 9; i++) { tg[i] = __ldg(reinterpret_cast<const uint32_t*>(prm.gate_w) + i * 32 + lane); t1[i] = __ldg(b1w + i * 32 + lane); }
                    const uint32_t t2 = __ldg(b2w + 32 * j + lane), t3 = __ldg(b2w + 256 + lane);
#pragma unroll
                    for (int i = 0; i < 9; i++) {
                        reinterpret_cast<uint32_t*>(smem_raw + OFF_GW)[i * 32 + lane] = tg[i];
                        reinterpret_cast<float2*>(smem_raw + OFF_B1)[i * 32 + lane] = make_float2(bf_lo(t1[i]), bf_hi(t1[i]));
                    }
                    reinterpret_cast<float2*>(smem_raw + OFF_B2)[lane] = make_float2(bf_lo(t2), bf_hi(t2));
                    reinterpret_cast<float2*>(smem_raw + OFF_B2)[32 + lane] = make_float2(bf_lo(t3), bf_hi(t3));
                    epoch = __shfl_sync(0xffffffff, epoch, 0);
                    if (lane == 0) asm volatile("st.shared.u32 [%0], %1;" :: "r"(sb + OFF_EPOCH), "r"(epoch) : "memory");
                    __syncwarp();
                    if (lane == 0) mbar_arrive(sb + B_XQDONE);
                }
                const char* p1 = reinterpret_cast<const char*>(prm.w1) + (size_t)(m * 36) * 9216 + j * 1152;
                const char* p2 = reinterpret_cast<const char*>(prm.w2) + (size_t)(576 * j + m * 36) * 1152;
                auto pf_w1 = [&](int g0, int g1) {
#pragma unroll 1
                    for (int g = g0; g < g1; g++) {
                        asm volatile("prefetch.global.L2 [%0];" :: "l"(p1 + lane * 9216 + g * 128));
                        if (lane < 4) asm volatile("prefetch.global.L2 [%0];" :: "l"(p1 + (32 + lane) * 9216 + g * 128));
                    }
                };
                auto pf_lin = [&](const char* p, int n) {
#pragma unroll 1
                    for (int i = lane; i < n; i += 32) asm volatile("prefetch.global.L2 [%0];" :: "l"(p + i * 128));
                };
                mbar_wait(sb + B_XFULL + 5 * 8, 0);
                pf_w1(0, 2);
                mbar_wait(sb + B_XFULL + 8 * 8, 0);
                pf_w1(2, 4);
                if (lane == 0) {
                    mbar_wait(sb + B_QDONE, 0);
                    red_release_add(cntA + m * 32, 1);
                }
                __syncwarp();
                pf_w1(4, 9);
                if (lane < 2 && m >= lane) wait_flag(cntA + (m - lane) * 32, epoch * 8);
                __syncwarp();
                if (lane == 0) { mbar_arrive(sb + B_QKV); }
                if (lane == 0) {
                    mbar_wait(sb + B_ODONE, 0);
                    red_release_add(cntO + m * 32, 1);
                }
                __syncwarp();
                pf_lin(p2, 324);
                pf_lin(reinterpret_cast<const char*>(prm.wo) + (size_t)(j * 16 + m) * 5184, 41);
                __syncwarp();
            }
            uint32_t* pfl = g_pflag + m * 9 * 64;
            if (hw == 2) {
                if (lane == 0) {
                    const CUtensorMap* mwo = typeB ? &mwoB : &mwoA;
                    const int half = typeB ? 16 : 48, r0 = typeB ? 320 + 32 * j : 96 * j;
                    wait_flag(cntO + m * 32, epoch * 8);
                    fence_proxy_async();
                    mbar_wait(sb + B_XDEAD, 0);
                    mbar_expect_tx(sb + B_WO0, half * 768);
                    tma3d_mc(sb + OFF_WO + rank * half * 128, mwo, 0, r0 + rank * half, 8, sb + B_WO0);
                    tma3d(sb + OFF_OT, typeB ? &moB : &moA, 0, r0, 2 * m, sb + B_WO0);
                    tma3d(sb + OFF_OT + SLOT, typeB ? &moB : &moA, 0, r0, 2 * m + 1, sb + B_WO0);
                    mbar_expect_tx(sb + B_WO1, half * 256 * 8);
#pragma unroll 1
                    for (int p = 1; p < 9; p++)
                        tma3d_mc(sb + OFF_WO + p * SLOT + rank * half * 128, mwo, 0, r0 + rank * half, (j + p) & 7, sb + B_WO1);
                    _Pragma("unroll 1") for (int p = 0; p < 8; p++) {
                        mbar_wait(sb + B_PDONE + p * 8, 0);
                        const int c = p == 0 ? 8 : ((j + p) & 7);
                        st_release(pfl + (c * 8 + j) * 8, epoch);
                    }
                }
            } else {
              if (hw == 0) {
                if (lane < 8) wait_flag(pfl + (64 + lane) * 8, epoch);
                __syncwarp();
                const int r = (j >> 2) * 64 + (j & 3) * 16 + (lane >> 2);
                const float s0 = 1.0f - lds_f(sb + OFF_G + r * 4), s1 = 1.0f - lds_f(sb + OFF_G + (r + 8) * 4);
                const int row = m * 128 + 2 * (r & 63) + (j >> 2);
                uint32_t* o32 = reinterpret_cast<uint32_t*>(prm.out + (size_t)row * D_ + 512) + (lane & 3);
                const uint4* src = g_part + (size_t)((m * 9 + 8) * 8) * 1024 + j * 128 + lane;
#pragma unroll 1
                for (int i = 0; i < 4; i++) {
                    float a[8];
                    const float2 ba = lds_f2(sb + OFF_B2 + (64 + i * 16 + (lane & 3) * 2) * 4), bb = lds_f2(sb + OFF_B2 + (64 + i * 16 + 8 + (lane & 3) * 2) * 4);
                    a[0] = s0 * ba.x; a[1] = s0 * ba.y; a[2] = s1 * ba.x; a[3] = s1 * ba.y;
                    a[4] = s0 * bb.x; a[5] = s0 * bb.y; a[6] = s1 * bb.x; a[7] = s1 * bb.y;
#pragma unroll 4
                    for (int js = 0; js < 8; js++) {
                        const uint4 v = __ldcg(src + js * 1024 + i * 32);
                        a[0] += bf_lo(v.x); a[1] += bf_hi(v.x); a[2] += bf_lo(v.y); a[3] += bf_hi(v.y);
                        a[4] += bf_lo(v.z); a[5] += bf_hi(v.z); a[6] += bf_lo(v.w); a[7] += bf_hi(v.w);
                    }
                    o32[i * 8] = pack_bf16(a[0], a[1]);
                    o32[i * 8 + 16 * (D_ / 2)] = pack_bf16(a[2], a[3]);
                    o32[i * 8 + 4] = pack_bf16(a[4], a[5]);
                    o32[i * 8 + 4 + 16 * (D_ / 2)] = pack_bf16(a[6], a[7]);
                }
              }
#pragma unroll 1
                for (int p = hw ? 1 : 7; p < (hw ? 7 : 8); p++) {
                    const int js = (j - p) & 7;
                    if (lane == 0) {
                        wait_flag(pfl + (j * 8 + js) * 8, epoch);
                        asm volatile("fence.proxy.async.global;" ::: "memory");
                        mbar_wait(sb + B_PDONE + p * 8, 0);
                        mbar_expect_tx(sb + B_PFULL + p * 8, 16384);
                        bulk_load(sb + ((p - 1) % 3) * 16384, g_part + (size_t)((m * 9 + j) * 8 + js) * 1024, 16384, sb + B_PFULL + p * 8);
                    }
                }
            }
        }
    } else {
        asm volatile("setmaxnreg.inc.sync.aligned.u32 232;");
        const int wg = warp >> 2, wq = warp & 3;
        const uint32_t da0 = desc_lo(sb + OFF_X + wg * 8192, 16);
        const uint32_t db0 = desc_lo(sb + OFF_RING, 2048);
        const bool do_rel = lane == 0 && wq < 2;
        const uint32_t rel = mapa(sb + B_EMPTY, wq & 1);
        float accA[32], accB[32];
        uint32_t h[128];
        uint32_t ph;
        uint32_t* qdst = g_qs + ((size_t)(lane & 3) * 2 + wg) * QP + 32 + m * 64 + wq * 16 + (lane >> 2);
        const uint32_t db1 = desc_lo(sb + OFF_RING, 6144);
        const uint32_t bias = sb + OFF_B1 + (lane & 3) * 8;
        float pa[64], pb[64];
        {
            float q[96];
#pragma unroll 1
            for (int r = 0; r < 3; r++) {
                const uint32_t da = da0 + r * 3072;
                static_for<0, 6>([&](auto sc) {
                    constexpr int s = sc.value;
                    if (!(s & 1)) mbar_wait(sb + B_XFULL + (r * 3 + (s >> 1)) * 8, 0);
                    mbar_wait(sb + B_FULL + s * 8, r & 1);
                    wgmma_fence();
                    wgmma_ss_n192<(s >> 1) * 16384 + (s & 1) * 64, s * SLOT>(q, da, db0, (r | s) != 0);
                    wgmma_ss_n192<(s >> 1) * 16384 + (s & 1) * 64 + 32, s * SLOT + 6144>(q, da, db0, 1);
                    wgmma_commit();
                    wgmma_wait<1>();
                    if (do_rel && (r | s) != 0) mbar_arrive_remote(rel + ((s + 5) % 6) * 8);
                });
            }
            float xq[32];
            ph = 1;
            if (typeB) {
#pragma unroll 1
                for (int s = 0; s < 6; s += 2) {
                    const uint32_t da = da0 + s * 1536, db = db0 + s * (SLOT / 16);
                    static_for<0, 2>([&](auto uc) {
                        constexpr int u = uc.value;
                        mbar_wait(sb + B_FULL + (s + u) * 8, 1);
                        wgmma_fence();
                        static_for<0, 6>([&](auto kc) {
                            constexpr int k = u * 6 + kc.value;
                            wgmma_ss_n64<(k >> 2) * 16384 + (k & 3) * 32, u * SLOT + kc.value * 2048>(xq, da, db, (s | k) != 0);
                        });
                        wgmma_commit();
                        wgmma_wait<1>();
                        if (do_rel) mbar_arrive_remote(rel + ((s | u) != 0 ? s + u - 1 : 5) * 8);
                    });
                }
                ph = 0;
            }
            mbar_wait(sb + B_FULL, ph);
            wgmma_wait<0>();
            fence_regs(q);
            fence_regs(xq);
            uint32_t* qd = qdst + (size_t)(96 * j) * 2 * QP;
            tile128<0, 12>(pa, sb, da0, db1, ph, rel, do_rel, [&](int i) {
                if (i <= 8) {
#pragma unroll
                    for (int g = i * 3 - 3; g < i * 3; g++) {
                        qd[g * 8 * QP] = pack_bf16(q[g * 4], q[g * 4 + 1]);
                        qd[g * 8 * QP + 8] = pack_bf16(q[g * 4 + 2], q[g * 4 + 3]);
                    }
                }
                if (i == 9) {
                    if (typeB) {
                        uint32_t* xd = qdst + (size_t)(32 * (19 + j)) * 2 * QP;
#pragma unroll
                        for (int g = 0; g < 8; g++) {
                            xd[g * 8 * QP] = pack_bf16(xq[g * 4], xq[g * 4 + 1]);
                            xd[g * 8 * QP + 8] = pack_bf16(xq[g * 4 + 2], xq[g * 4 + 3]);
                        }
                    }
                    __syncwarp();
                    if (lane == 0) mbar_arrive(sb + B_QDONE);
                }
            });
        }
        mbar_wait(sb + B_GATE, 0);
        const int r0 = wg * 64 + wq * 16 + (lane >> 2);
        const float s0 = 0.5f - 0.5f * lds_f(sb + OFF_G + r0 * 4), s1 = 0.5f - 0.5f * lds_f(sb + OFF_G + (r0 + 8) * 4);
        auto gelu_group = [&](const float* a, float2 b, uint32_t* dst) {
            dst[0] = pack_bf16(gelu_scaled(a[0] + b.x, s0), gelu_scaled(a[1] + b.y, s0));
            dst[1] = pack_bf16(gelu_scaled(a[2] + b.x, s1), gelu_scaled(a[3] + b.y, s1));
        };
        float2 nb[2];
        auto chunk128 = [&](float (&a)[64], int i, uint32_t* dst, uint32_t baddr) {
            if (i == 1) fence_regs(a);
            const int g0 = i <= 6 ? 2 * i - 2 : i + 4, g1 = i <= 5 ? 2 * i : i + 5;
            const float2 b0 = nb[0], b1 = nb[1];
            if (i < 11) nb[0] = lds_f2(baddr + g1 * 32);
            if (i < 5) nb[1] = lds_f2(baddr + g1 * 32 + 32);
            gelu_group(&a[4 * g0], b0, &dst[2 * g0]);
            if (g1 - g0 == 2) gelu_group(&a[4 * g0 + 4], b1, &dst[2 * g0 + 2]);
        };
#pragma unroll 1
        for (int it = 0;; it++) {
        nb[0] = lds_f2(bias + it * 512); nb[1] = lds_f2(bias + it * 512 + 32);
        tile128<0, 12>(pb, sb, da0, db1, ph, rel, do_rel, [&](int i) { chunk128(pa, i, &h[32], bias + it * 512); });
        wgmma_wait<0>();
        fence_regs(pb);
        if (it == 1) break;
        {
            constexpr int KO = 288 * QP;
            const int hd = 4 * j + (warp >> 1), p = warp & 1;
            const uint2* kp = reinterpret_cast<const uint2*>(g_qs + (hd * 18 + p) * QP + 24 + m * 64) + KO + lane;
            mbar_wait(sb + B_QKV, 0);
            constexpr int AW = 5;
            uint2 w[AW][6];
            auto load_row = [&](int r) {
                const uint2* a = r < 9 ? kp + r * QP : kp + KO + (r - 9) * QP;
#pragma unroll
                for (int u = 0; u < 5; u++) w[r % AW][u] = a[u];
                if (r < 9) w[r % AW][5] = a[4 - KO];
            };
#pragma unroll
            for (int r = 0; r < AW; r++) load_row(r);
            float la[8], lb[8];
#pragma unroll
            for (int i = 0; i < 8; i++) { la[i] = 0.f; lb[i] = 0.f; }
#pragma unroll
            for (int r = 0; r < 9; r++) {
                const uint2 (&c)[6] = w[r % AW];
                const float qa0 = bf_lo(c[5].x), qa1 = bf_hi(c[5].x), qb0 = bf_lo(c[5].y), qb1 = bf_hi(c[5].y);
#pragma unroll
                for (int t = 1; t < 10; t++) {
                    const uint32_t kw = (t & 1) ? c[t >> 1].y : c[t >> 1].x;
                    const float k0 = bf_lo(kw), k1 = bf_hi(kw);
                    if (t <= 8) la[t - 1] = fmaf(qa1, k1, fmaf(qa0, k0, la[t - 1]));
                    if (t >= 2) lb[t - 2] = fmaf(qb1, k1, fmaf(qb0, k0, lb[t - 2]));
                }
                load_row(r + AW);
            }
            const int i0 = m * 64 + 2 * lane;
            const float sc = 0.23570226039551584f * 1.4426950408889634f;
            float ma = la[7], mb = lb[7];
#pragma unroll
            for (int i = 0; i < 7; i++) {
                if (i0 - 7 + i < 0) la[i] = -INFINITY;
                if (i0 - 6 + i < 0) lb[i] = -INFINITY;
                ma = fmaxf(ma, la[i]); mb = fmaxf(mb, lb[i]);
            }
            float sa = 0.f, sbm = 0.f;
#pragma unroll
            for (int i = 0; i < 8; i++) {
                la[i] = ex2f((la[i] - ma) * sc); sa += la[i];
                lb[i] = ex2f((lb[i] - mb) * sc); sbm += lb[i];
            }
            const float2 gg = lds_f2(sb + OFF_G + (p * 64 + 2 * lane) * 4);
            const float fa = __fdividef(gg.x, sa), fb = __fdividef(gg.y, sbm);
#pragma unroll
            for (int i = 0; i < 8; i++) { la[i] *= fa; lb[i] *= fb; }
            uint32_t* op = reinterpret_cast<uint32_t*>(g_oT + (size_t)hd * 18 * 2048 + m * 128 + p * 64) + lane;
#pragma unroll
            for (int r = 9; r < 18; r++) {
                const uint2 (&c)[6] = w[r % AW];
                float a0 = 0.f, a1 = 0.f, b0 = 0.f, b1 = 0.f;
#pragma unroll
                for (int t = 1; t < 10; t++) {
                    const uint32_t vw = (t & 1) ? c[t >> 1].y : c[t >> 1].x;
                    const float v0 = bf_lo(vw), v1 = bf_hi(vw);
                    if (t <= 8) { a0 = fmaf(la[t - 1], v0, a0); a1 = fmaf(la[t - 1], v1, a1); }
                    if (t >= 2) { b0 = fmaf(lb[t - 2], v0, b0); b1 = fmaf(lb[t - 2], v1, b1); }
                }
                if (r + AW < 18) load_row(r + AW);
                op[(r - 9) * 2048] = pack_bf16(a0, b0);
                op[(r - 9) * 2048 + 1024] = pack_bf16(a1, b1);
            }
            __syncwarp();
            if (lane == 0) mbar_arrive(sb + B_ODONE);
#pragma unroll
            for (int i = 0; i < 32; i++) h[i] = h[32 + i];
        }
#pragma unroll
        for (int i = 0; i < 64; i++) pa[i] = pb[i];
        }
        float2 bv[2];
        tile_ss<0, 6>(accA, sb, da0, db0, ph, rel, do_rel,
            [&](int s) { bv[0] = lds_f2(bias + 1024 + s * 64); bv[1] = lds_f2(bias + 1024 + s * 64 + 32); },
            [&](int s) { gelu_group(&pb[8 * s], bv[0], &h[64 + 4 * s]); gelu_group(&pb[8 * s + 4], bv[1], &h[66 + 4 * s]); });
        auto pre64 = [&](int s, uint32_t baddr) {
#pragma unroll
            for (int g = 0; g < (s < 2 ? 2 : 1); g++) bv[g] = lds_f2(baddr + ((s < 2 ? 2 * s : s + 2) + g) * 32);
        };
        auto epi64 = [&](float (&a)[32], int s, uint32_t* dst) {
            if (s == 0) fence_regs(a);
#pragma unroll
            for (int g = 0; g < (s < 2 ? 2 : 1); g++) gelu_group(&a[4 * ((s < 2 ? 2 * s : s + 2) + g)], bv[g], &dst[2 * ((s < 2 ? 2 * s : s + 2) + g)]);
        };
        tile_ss<0, 6>(accB, sb, da0, db0, ph ^ 1, rel, do_rel,
            [&](int s) { bv[0] = lds_f2(bias + 1408 + s * 64); bv[1] = lds_f2(bias + 1408 + s * 64 + 32); },
            [&](int s) {
                if (s < 2) {
                    gelu_group(&pb[48 + 8 * s], bv[0], &h[88 + 4 * s]); gelu_group(&pb[52 + 8 * s], bv[1], &h[90 + 4 * s]);
                } else {
                    if (s == 2) fence_regs(accA);
                    gelu_group(&accA[8 * (s - 2)], bv[0], &h[88 + 4 * s]); gelu_group(&accA[8 * (s - 2) + 4], bv[1], &h[90 + 4 * s]);
                }
            });
        tile_ss<0, 6>(accA, sb, da0, db0, ph, rel, do_rel, [&](int s) { pre64(s, bias + 1792); }, [&](int s) { epi64(accB, s, &h[112]); });
        ph ^= 1;
        const uint32_t dot = desc_lo(sb + OFF_OT + wg * SLOT, 16);
        uint32_t dwo = desc_lo(sb + OFF_WO, 16);
        const int srow = (lane & 7) + ((lane >> 3) & 1) * 8;
        wgmma_wait<0>();
        if (do_rel) { mbar_arrive_remote(rel + 5 * 8); mbar_arrive_remote(mapa(sb + B_XDEAD, wq & 1)); }
        fence_regs(accA);
        nb[0] = lds_f2(bias + 2048); nb[1] = lds_f2(bias + 2080);
        uint4* pdst = g_part + (size_t)(m * 9 * 8 + j) * 1024 + warp * 128 + lane;
        const uint32_t pbuf = sb + warp * 2048 + lane * 16;
        auto add_partial = [&](int p, int i0, int i1) {
            if (i0 == 0) mbar_wait(sb + B_PFULL + p * 8, 0);
#pragma unroll
            for (int i = i0; i < i1; i++) {
                const uint4 v = lds_u4(pbuf + ((p - 1) % 3) * 16384 + i * 512);
                accA[i * 8] += bf_lo(v.x); accA[i * 8 + 1] += bf_hi(v.x); accA[i * 8 + 2] += bf_lo(v.y); accA[i * 8 + 3] += bf_hi(v.y);
                accA[i * 8 + 4] += bf_lo(v.z); accA[i * 8 + 5] += bf_hi(v.z); accA[i * 8 + 6] += bf_lo(v.w); accA[i * 8 + 7] += bf_hi(v.w);
            }
        };
        if (wg == 1) { const int c0 = (int)clock(); while ((int)clock() - c0 < 200); }
#pragma unroll 1
        for (int p = 0;; p++) {
            pass_rs(accB, h, sb, da0, db0, dot, dwo, typeB, sb + (p == 0 ? B_WO0 : B_WO1), ph, rel, do_rel, p < 8, [&](int s) {
                if (p == 0) {
                    if (s < 4) {
                        uint32_t w[4];
                        const float2 b0 = nb[0], b1 = nb[1];
                        if (s < 3) { nb[0] = lds_f2(bias + 2112 + s * 64); nb[1] = lds_f2(bias + 2112 + s * 64 + 32); }
                        gelu_group(&accA[8 * s], b0, &w[0]);
                        gelu_group(&accA[8 * s + 4], b1, &w[2]);
                        const int row = wq * 16 + srow;
                        asm volatile("stmatrix.sync.aligned.m8n8.x4.shared.b16 [%0], {%1, %2, %3, %4};"
                            :: "r"(sb + OFF_X + 8 * 16384 + wg * 8192 + row * 128 + (((s * 2 + (lane >> 4)) ^ (row & 7)) << 4)),
                               "r"(w[0]), "r"(w[1]), "r"(w[2]), "r"(w[3]) : "memory");
                        const float2 c0 = lds_f2(sb + OFF_B2 + (s * 16 + (lane & 3) * 2) * 4), c1 = lds_f2(sb + OFF_B2 + (s * 16 + 8 + (lane & 3) * 2) * 4);
                        accA[8 * s] = 2.f * s0 * c0.x; accA[8 * s + 1] = 2.f * s0 * c0.y; accA[8 * s + 2] = 2.f * s1 * c0.x; accA[8 * s + 3] = 2.f * s1 * c0.y;
                        accA[8 * s + 4] = 2.f * s0 * c1.x; accA[8 * s + 5] = 2.f * s0 * c1.y; accA[8 * s + 6] = 2.f * s1 * c1.x; accA[8 * s + 7] = 2.f * s1 * c1.y;
                    }
                    if (s == 4) {
                        asm volatile("fence.proxy.async.shared::cta;" ::: "memory");
                        asm volatile("bar.sync %0, 128;" :: "r"(2 + wg) : "memory");
                    }
                } else if ((s == 2 || s == 3) && p >= 4) {
                    add_partial(p - 3, s * 2 - 4, s * 2 - 2);
                } else if (s >= 4 && p == 8) {
                    add_partial(6, s * 2 - 8, s * 2 - 6);
                }
            });
            fence_regs(accB);
            if (p == 8) break;
            uint4* d = pdst + (size_t)(p == 0 ? 8 : ((j + p) & 7)) * 8 * 1024;
#pragma unroll
            for (int i = 0; i < 4; i++)
                d[i * 32] = make_uint4(pack_bf16(accB[i * 8], accB[i * 8 + 1]), pack_bf16(accB[i * 8 + 2], accB[i * 8 + 3]),
                                       pack_bf16(accB[i * 8 + 4], accB[i * 8 + 5]), pack_bf16(accB[i * 8 + 6], accB[i * 8 + 7]));
            __syncwarp();
            if (lane == 0) mbar_arrive(sb + B_PDONE + p * 8);
            dwo += SLOT / 16;
            ph ^= 1;
        }
        add_partial(7, 0, 4);
        const uint32_t stg = sb + 16384 + warp * 2048;
        {
#pragma unroll
            for (int i = 0; i < 4; i++) {
                const uint32_t w0 = pack_bf16(accB[i * 8] + accA[i * 8], accB[i * 8 + 1] + accA[i * 8 + 1]);
                const uint32_t w1 = pack_bf16(accB[i * 8 + 2] + accA[i * 8 + 2], accB[i * 8 + 3] + accA[i * 8 + 3]);
                const uint32_t w2 = pack_bf16(accB[i * 8 + 4] + accA[i * 8 + 4], accB[i * 8 + 5] + accA[i * 8 + 5]);
                const uint32_t w3 = pack_bf16(accB[i * 8 + 6] + accA[i * 8 + 6], accB[i * 8 + 7] + accA[i * 8 + 7]);
                const int chunk = i * 2 + (lane >> 4);
                asm volatile("stmatrix.sync.aligned.m8n8.x4.shared.b16 [%0], {%1, %2, %3, %4};"
                    :: "r"(stg + srow * 128 + ((chunk ^ (srow & 7)) << 4)), "r"(w0), "r"(w1), "r"(w2), "r"(w3) : "memory");
            }
            __syncwarp();
#pragma unroll
            for (int i = 0; i < 4; i++) {
                const int rr = i * 4 + (lane >> 3), ch = lane & 7;
                const uint4 v = lds_u4(stg + rr * 128 + ((ch ^ (rr & 7)) << 4));
                const int row = m * 128 + 2 * (wq * 16 + rr) + wg;
                *reinterpret_cast<uint4*>(prm.out + (size_t)row * D_ + 64 * j + ch * 8) = v;
            }
        }
    }
}

typedef CUresult (*EncodeFn)(CUtensorMap*, CUtensorMapDataType, cuuint32_t, void*, const cuuint64_t*, const cuuint64_t*, const cuuint32_t*,
                             const cuuint32_t*, CUtensorMapInterleave, CUtensorMapSwizzle, CUtensorMapL2promotion, CUtensorMapFloatOOBfill);

void encode3d(EncodeFn enc, CUtensorMap* m, const void* ptr, uint64_t d0, uint64_t d1, uint64_t d2, uint64_t s1, uint64_t s2,
              uint32_t b0, uint32_t b1, uint32_t b2) {
    cuuint64_t dims[3] = {d0, d1, d2}, str[2] = {s1, s2};
    cuuint32_t box[3] = {b0, b1, b2}, es[3] = {1, 1, 1};
    enc(m, CU_TENSOR_MAP_DATA_TYPE_BFLOAT16, 3, const_cast<void*>(ptr), dims, str, box, es, CU_TENSOR_MAP_INTERLEAVE_NONE,
        CU_TENSOR_MAP_SWIZZLE_128B, CU_TENSOR_MAP_L2_PROMOTION_L2_256B, CU_TENSOR_MAP_FLOAT_OOB_FILL_NONE);
}
void encode_groups(EncodeFn enc, CUtensorMap* m, const void* ptr, uint64_t rows, uint64_t cols, uint32_t box_rows, uint32_t box_groups) {
    encode3d(enc, m, ptr, 64, rows, cols / 64, cols * 2, 128, 64, box_rows, box_groups);
}

}

extern "C" void kernel_launch(void* const* d_in, const int* in_sizes, int n_in, void* d_out, int out_size) {
    void* fn = nullptr;
    cudaDriverEntryPointQueryResult qr;
    cudaGetDriverEntryPoint("cuTensorMapEncodeTiled", &fn, cudaEnableDefault, &qr);
    EncodeFn enc = (EncodeFn)fn;
    void* oT = nullptr;
    cudaGetSymbolAddress(&oT, g_oT);
    CUtensorMap mx, mq3, mq1, mw1, mw2, mwoA, mwoB, moA, moB;
    encode3d(enc, &mx, d_in[0], 576, 1024, 2, 2304, 1152, 64, 64, 2);
    encode_groups(enc, &mq3, d_in[1], 576, 1728, 16, 3);
    encode_groups(enc, &mq1, d_in[1], 576, 1728, 48, 1);
    encode_groups(enc, &mw1, d_in[4], 576, 4608, 48, 1);
    encode_groups(enc, &mw2, d_in[6], 4608, 576, 48, 1);
    encode_groups(enc, &mwoA, d_in[2], 576, 576, 48, 1);
    encode_groups(enc, &mwoB, d_in[2], 576, 576, 16, 1);
    encode_groups(enc, &moA, oT, 576, 2048, 96, 1);
    encode_groups(enc, &moB, oT, 576, 2048, 32, 1);
    Params prm;
    prm.b1 = (const __nv_bfloat16*)d_in[5];
    prm.b2 = (const __nv_bfloat16*)d_in[7];
    prm.gate_w = (const __nv_bfloat16*)d_in[8];
    prm.w1 = (const __nv_bfloat16*)d_in[4];
    prm.w2 = (const __nv_bfloat16*)d_in[6];
    prm.wo = (const __nv_bfloat16*)d_in[2];
    prm.out = (__nv_bfloat16*)d_out;
    cudaFuncSetAttribute(fused_kernel, cudaFuncAttributeMaxDynamicSharedMemorySize, SMEM_BYTES);
    fused_kernel<<<128, 384, SMEM_BYTES, cudaStreamPerThread>>>(mx, mq3, mq1, mw1, mw2, mwoA, mwoB, moA, moB, prm);
}
```
